```python
import torch

def _softmax(x, axis=-1):
    return torch.softmax(x, dim=axis)
def _gelu(x):
    return torch.nn.functional.gelu(x, approximate="tanh")
def _silu(x):
    return torch.nn.functional.silu(x)
def _sigmoid(x):
    return torch.sigmoid(x)
def _layernorm(x, axis=-1, eps=1e-5):
    m = x.mean(dim=axis, keepdim=True)
    v = x.var(dim=axis, keepdim=True, unbiased=False)
    return (x - m) / torch.sqrt(v + eps)
def _scatter_add(tgt, idx, src, axis=0):
    return tgt.clone().index_add_(axis, idx, src)
def _segment_sum(src, seg, n):
    out = torch.zeros((n,) + src.shape[1:], dtype=src.dtype)
    return out.index_add_(0, seg, src)
def _pad(x, pw):
    flat = tuple(v for pair in reversed(pw) for v in pair)
    return torch.nn.functional.pad(x, flat)

kernel_name = 'gated_mix__ssm_conv_s4d__dense_activation_relu__prompt'

def setup_inputs():

    _w = (lambda a: (lambda t: t.to(torch.bfloat16) if t.is_floating_point() else t)(torch.as_tensor(a)))
    def _A_setup():
        Bsz, L, D, N = 1, 2048, 640, 128
        return {
            "u": _w((lambda *s: torch.randn(*s, dtype=torch.bfloat16) * 0.05)(Bsz, L, D)),
            "log_A_real": _w((lambda *s: torch.randn(*s, dtype=torch.bfloat16) * 6.4)(D, N) * 0.5),
            "A_imag": _w((lambda *s: torch.randn(*s, dtype=torch.bfloat16) * 0.2)(D, N) * 3.14),
            "C_real": _w((lambda *s: torch.randn(*s, dtype=torch.bfloat16) * 0.8)(D, N) / N ** 0.5),
            "C_imag": _w((lambda *s: torch.randn(*s, dtype=torch.bfloat16) * 0.8)(D, N) / N ** 0.5),
            "log_dt": _w((lambda *s: torch.randn(*s, dtype=torch.bfloat16) * 0.2)(D) * 0.5 - 4.0),
            "D_skip": _w((lambda *s: torch.randn(*s, dtype=torch.bfloat16) * 0.2)(D)),
        }
    _A_in = _A_setup()

    def _B_setup():
        B, S, D, Dff = 1, 2048, 640, 1728
        return {
            "x": _w((lambda *s: torch.randn(*s, dtype=torch.bfloat16) * 0.05)(B, S, D)),
            "w1": _w((lambda *s: torch.randn(*s, dtype=torch.bfloat16) * 0.05)(D, Dff)),
            "w2": _w((lambda *s: torch.randn(*s, dtype=torch.bfloat16) * 0.05)(Dff, D)),
        }
    _B_in = _B_setup()

    return {
        "A_u": _A_in["u"],
        "A_log_A_real": _A_in["log_A_real"],
        "A_A_imag": _A_in["A_imag"],
        "A_C_real": _A_in["C_real"],
        "A_C_imag": _A_in["C_imag"],
        "A_log_dt": _A_in["log_dt"],
        "A_D_skip": _A_in["D_skip"],
        "B_x": _B_in["x"],
        "B_w1": _B_in["w1"],
        "B_w2": _B_in["w2"],
        "gate_w": _w((lambda *s: torch.randn(*s, dtype=torch.bfloat16) * 0.05)(640) * 16.0),
    }

def reference(A_u, A_log_A_real, A_A_imag, A_C_real, A_C_imag, A_log_dt, A_D_skip, B_x, B_w1, B_w2, gate_w):
    def _A_ref(u, log_A_real, A_imag, C_real, C_imag, log_dt, D_skip):
        L = u.shape[1]
        dt = torch.exp(log_dt)
        A = -torch.exp(log_A_real) + 1j * A_imag
        C = (C_real + 1j * C_imag) * dt[:, None]
        pos = (lambda x, dt: x.to(dt))(torch.arange(L), log_dt.dtype)
        P = torch.exp((A * dt[:, None])[:, :, None] * pos[None, None, :])
        K = 2.0 * torch.einsum("dn,dnl->dl", C, P).real
        L2 = 2 * L
        u_t = (lambda x, *d: x.permute(*d))(u, 0, 2, 1)
        Kf = (lambda x, *a, **k: torch.fft.rfft(x.float(), *a, **k))(K, L2)
        Uf = (lambda x, *a, **k: torch.fft.rfft(x.float(), *a, **k))(u_t, L2)
        y = (lambda x, *a, **k: torch.fft.irfft(x, *a, **k).to(torch.bfloat16))(Uf * Kf[None, :, :], L2)[:, :, :L]
        y = (lambda x, *d: x.permute(*d))(y, 0, 2, 1)
        return y + u * D_skip[None, None, :]

    def _B_ref(x, w1, w2):
        h = torch.einsum("bsd,df->bsf", x, w1)
        zero = torch.zeros_like(h)
        h = torch.maximum(h, zero)
        return torch.einsum("bsf,fd->bsd", h, w2)

    x = A_u
    g = _sigmoid((x * gate_w).sum(-1, keepdims=True))
    a = _A_ref(x, A_log_A_real, A_A_imag, A_C_real, A_C_imag, A_log_dt, A_D_skip)
    b = _B_ref(x, B_w1, B_w2)
    return g * a + (1 - g) * b
```

```cpp
#include <cuda_runtime.h>
#include <cuda.h>
#include <cuda_bf16.h>
#include <cuda_fp16.h>
#include <stdint.h>

namespace {

constexpr int L_=2048, DM=640, FF=1728, NM=128;

__device__ __forceinline__ uint32_t smem_u32(const void* p){ return (uint32_t)__cvta_generic_to_shared(p); }
__device__ __forceinline__ void wg_fence(){ asm volatile("wgmma.fence.sync.aligned;" ::: "memory"); }
__device__ __forceinline__ void wg_commit(){ asm volatile("wgmma.commit_group.sync.aligned;" ::: "memory"); }
template<int N> __device__ __forceinline__ void wg_wait(){ asm volatile("wgmma.wait_group.sync.aligned %0;" :: "n"(N) : "memory"); }
__device__ __forceinline__ uint64_t mkdesc(uint32_t addr, uint32_t lbo, uint32_t sbo, uint32_t swz){
  return (uint64_t)((addr&0x3FFFF)>>4) | ((uint64_t)(lbo>>4)<<16) | ((uint64_t)(sbo>>4)<<32) | ((uint64_t)swz<<62);
}
__device__ __forceinline__ void mbar_init(uint32_t bar, uint32_t cnt){ asm volatile("mbarrier.init.shared::cta.b64 [%0], %1;" :: "r"(bar), "r"(cnt) : "memory"); }
__device__ __forceinline__ void mbar_expect_tx(uint32_t bar, uint32_t bytes){ asm volatile("mbarrier.arrive.expect_tx.shared::cta.b64 _, [%0], %1;" :: "r"(bar), "r"(bytes) : "memory"); }
__device__ __forceinline__ void mbar_arrive(uint32_t bar){ asm volatile("mbarrier.arrive.shared::cta.b64 _, [%0];" :: "r"(bar) : "memory"); }
__device__ __forceinline__ void mbar_arrive_cluster(uint32_t bar, uint32_t cta){
  asm volatile("{\n.reg .b32 ra;\nmapa.shared::cluster.u32 ra, %0, %1;\nmbarrier.arrive.shared::cluster.b64 _, [ra];\n}" :: "r"(bar), "r"(cta) : "memory"); }
__device__ __forceinline__ void mbar_wait(uint32_t bar, uint32_t parity){
  asm volatile("{\n.reg .pred p;\n.reg .u32 n;\nmov.u32 n, 0;\nLAB_WAIT:\nmbarrier.try_wait.parity.shared::cta.b64 p, [%0], %1;\n@p bra LAB_DONE;\n"
               "add.u32 n, n, 1;\nsetp.lt.u32 p, n, 0x4000000;\n@p bra LAB_WAIT;\ntrap;\nLAB_DONE:\n}" :: "r"(bar), "r"(parity) : "memory"); }
__device__ __forceinline__ void wait_flag(const unsigned* p, unsigned target){
  asm volatile("{\n.reg .pred q;\n.reg .u32 v, n;\nmov.u32 n, 0;\nLAB_POLL:\nld.acquire.gpu.global.u32 v, [%0];\nsetp.ge.u32 q, v, %1;\n@q bra LAB_OK;\n"
               "nanosleep.u32 20;\nadd.u32 n, n, 1;\nsetp.lt.u32 q, n, 0x400000;\n@q bra LAB_POLL;\ntrap;\nLAB_OK:\n}" :: "l"(p), "r"(target) : "memory");
}
__device__ __forceinline__ void red_release(unsigned* p, unsigned v){ asm volatile("red.release.gpu.global.add.u32 [%0], %1;" :: "l"(p), "r"(v) : "memory"); }
__device__ __forceinline__ void red_relaxed(unsigned* p, unsigned v){ asm volatile("red.relaxed.gpu.global.add.u32 [%0], %1;" :: "l"(p), "r"(v) : "memory"); }
__device__ __forceinline__ void tma2d(uint32_t dst, const CUtensorMap* m, int c0, int c1, uint32_t bar){
  asm volatile("cp.async.bulk.tensor.2d.shared::cluster.global.mbarrier::complete_tx::bytes [%0], [%1, {%3, %4}], [%2];"
   :: "r"(dst), "l"(m), "r"(bar), "r"(c0), "r"(c1) : "memory"); }
__device__ __forceinline__ void tma3d(uint32_t dst, const CUtensorMap* m, int c0, int c1, int c2, uint32_t bar){
  asm volatile("cp.async.bulk.tensor.3d.shared::cluster.global.mbarrier::complete_tx::bytes [%0], [%1, {%3, %4, %5}], [%2];"
   :: "r"(dst), "l"(m), "r"(bar), "r"(c0), "r"(c1), "r"(c2) : "memory"); }
__device__ __forceinline__ void tma3d_mc(uint32_t dst, const CUtensorMap* m, int c0, int c1, int c2, uint32_t bar, uint16_t mask){
  asm volatile("cp.async.bulk.tensor.3d.shared::cluster.global.mbarrier::complete_tx::bytes.multicast::cluster [%0], [%1, {%3, %4, %5}], [%2], %6;"
   :: "r"(dst), "l"(m), "r"(bar), "r"(c0), "r"(c1), "r"(c2), "h"(mask) : "memory"); }
__device__ __forceinline__ void tma3d_store(const CUtensorMap* m, uint32_t src, int c0, int c1, int c2){
  asm volatile("cp.async.bulk.tensor.3d.global.shared::cta.bulk_group [%0, {%2, %3, %4}], [%1];" :: "l"(m), "r"(src), "r"(c0), "r"(c1), "r"(c2) : "memory"); }
__device__ __forceinline__ void bulk_g2s(uint32_t dst, const void* src, uint32_t bytes, uint32_t bar){
  asm volatile("cp.async.bulk.shared::cluster.global.mbarrier::complete_tx::bytes [%0], [%1], %2, [%3];"
   :: "r"(dst), "l"(src), "r"(bytes), "r"(bar) : "memory"); }
__device__ __forceinline__ void bulk_s2g(void* dst, uint32_t src, uint32_t bytes){
  asm volatile("cp.async.bulk.global.shared::cta.bulk_group [%0], [%1], %2;" :: "l"(dst), "r"(src), "r"(bytes) : "memory"); }
__device__ __forceinline__ void bulk_commit(){ asm volatile("cp.async.bulk.commit_group;" ::: "memory"); }
__device__ __forceinline__ void bulk_wait_read(){ asm volatile("cp.async.bulk.wait_group.read 0;" ::: "memory"); }
__device__ __forceinline__ void bulk_wait_all(){ asm volatile("cp.async.bulk.wait_group 0;" ::: "memory"); }
__device__ __forceinline__ void fence_async_smem(){ asm volatile("fence.proxy.async.shared::cta;" ::: "memory"); }
__device__ __forceinline__ void fence_async_global(){ asm volatile("fence.proxy.async.global;" ::: "memory"); }
__device__ __forceinline__ bool elect_one(){ uint32_t p; asm volatile("{\n.reg .pred P;\nelect.sync _|P, 0xffffffff;\nselp.u32 %0, 1, 0, P;\n}" : "=r"(p)); return p!=0; }
#define named_bar(id,n) asm volatile("bar.sync " #id ", " #n ";" ::: "memory")

__device__ __forceinline__ void ldsm4(uint32_t a, uint32_t& r0,uint32_t& r1,uint32_t& r2,uint32_t& r3){
  asm volatile("ldmatrix.sync.aligned.m8n8.x4.shared.b16 {%0,%1,%2,%3},[%4];":"=r"(r0),"=r"(r1),"=r"(r2),"=r"(r3):"r"(a)); }
__device__ __forceinline__ void ldsm4t(uint32_t a, uint32_t& r0,uint32_t& r1,uint32_t& r2,uint32_t& r3){
  asm volatile("ldmatrix.sync.aligned.m8n8.x4.trans.shared.b16 {%0,%1,%2,%3},[%4];":"=r"(r0),"=r"(r1),"=r"(r2),"=r"(r3):"r"(a)); }
__device__ __forceinline__ void stsm4(uint32_t a, uint32_t r0,uint32_t r1,uint32_t r2,uint32_t r3){
  asm volatile("stmatrix.sync.aligned.m8n8.x4.shared.b16 [%0],{%1,%2,%3,%4};"::"r"(a),"r"(r0),"r"(r1),"r"(r2),"r"(r3):"memory"); }
__device__ __forceinline__ void stsm4t(uint32_t a, uint32_t r0,uint32_t r1,uint32_t r2,uint32_t r3){
  asm volatile("stmatrix.sync.aligned.m8n8.x4.trans.shared.b16 [%0],{%1,%2,%3,%4};"::"r"(a),"r"(r0),"r"(r1),"r"(r2),"r"(r3):"memory"); }
__device__ __forceinline__ void mma_bf(float (&d)[4], uint32_t a0,uint32_t a1,uint32_t a2,uint32_t a3,uint32_t b0,uint32_t b1){
  asm volatile("mma.sync.aligned.m16n8k16.row.col.f32.bf16.bf16.f32 {%0,%1,%2,%3},{%4,%5,%6,%7},{%8,%9},{%0,%1,%2,%3};"
   : "+f"(d[0]),"+f"(d[1]),"+f"(d[2]),"+f"(d[3]) : "r"(a0),"r"(a1),"r"(a2),"r"(a3),"r"(b0),"r"(b1)); }
__device__ __forceinline__ void mma_hf(float (&d)[4], uint32_t a0,uint32_t a1,uint32_t a2,uint32_t a3,uint32_t b0,uint32_t b1){
  asm volatile("mma.sync.aligned.m16n8k16.row.col.f32.f16.f16.f32 {%0,%1,%2,%3},{%4,%5,%6,%7},{%8,%9},{%0,%1,%2,%3};"
   : "+f"(d[0]),"+f"(d[1]),"+f"(d[2]),"+f"(d[3]) : "r"(a0),"r"(a1),"r"(a2),"r"(a3),"r"(b0),"r"(b1)); }
__device__ __forceinline__ uint32_t lds32(uint32_t a){ uint32_t v; asm volatile("ld.shared.u32 %0,[%1];":"=r"(v):"r"(a)); return v; }
__device__ __forceinline__ uint32_t lds32v(uint32_t a){ uint32_t v; asm volatile("ld.volatile.shared.u32 %0,[%1];":"=r"(v):"r"(a)); return v; }
__device__ __forceinline__ float lds32f(uint32_t a){ float v; asm volatile("ld.shared.f32 %0,[%1];":"=f"(v):"r"(a)); return v; }
__device__ __forceinline__ void sts32f(uint32_t a, float v){ asm volatile("st.shared.f32 [%0],%1;"::"r"(a),"f"(v):"memory"); }
__device__ __forceinline__ uint4 lds128(uint32_t a){ uint4 v; asm volatile("ld.shared.v4.u32 {%0,%1,%2,%3},[%4];":"=r"(v.x),"=r"(v.y),"=r"(v.z),"=r"(v.w):"r"(a)); return v; }
__device__ __forceinline__ void sts32(uint32_t a, uint32_t v){ asm volatile("st.shared.u32 [%0],%1;"::"r"(a),"r"(v):"memory"); }
__device__ __forceinline__ void sts16(uint32_t a, uint32_t v){ asm volatile("st.shared.u16 [%0],%1;"::"r"(a),"h"((unsigned short)v):"memory"); }
__device__ __forceinline__ void sts64(uint32_t a, uint32_t v0, uint32_t v1){ asm volatile("st.shared.v2.u32 [%0],{%1,%2};"::"r"(a),"r"(v0),"r"(v1):"memory"); }
__device__ __forceinline__ void sts128(uint32_t a, uint32_t v0, uint32_t v1, uint32_t v2, uint32_t v3){ asm volatile("st.shared.v4.u32 [%0],{%1,%2,%3,%4};"::"r"(a),"r"(v0),"r"(v1),"r"(v2),"r"(v3):"memory"); }
__device__ __forceinline__ uint32_t pack_bf(float lo,float hi){ uint32_t r; asm("cvt.rn.bf16x2.f32 %0, %1, %2;":"=r"(r):"f"(hi),"f"(lo)); return r; }
__device__ __forceinline__ uint32_t pack_bf_relu(float lo,float hi){ uint32_t r; asm("cvt.rn.relu.bf16x2.f32 %0, %1, %2;":"=r"(r):"f"(hi),"f"(lo)); return r; }
__device__ __forceinline__ uint32_t pack_hf(float lo,float hi){ uint32_t r; asm("cvt.rn.f16x2.f32 %0, %1, %2;":"=r"(r):"f"(hi),"f"(lo)); return r; }
__device__ __forceinline__ float bflo(uint32_t w){ return __uint_as_float(w<<16); }
__device__ __forceinline__ float bfhi(uint32_t w){ return __uint_as_float(w&0xffff0000u); }
__device__ __forceinline__ float bf16r(float x){ return bflo(pack_bf(x,0.f)); }
__device__ __forceinline__ uint32_t bmul2(uint32_t a, uint32_t b){ uint32_t r; asm("mul.rn.bf16x2 %0, %1, %2;":"=r"(r):"r"(a),"r"(b)); return r; }
__device__ __forceinline__ uint32_t badd2(uint32_t a, uint32_t b){ uint32_t r; asm("add.rn.bf16x2 %0, %1, %2;":"=r"(r):"r"(a),"r"(b)); return r; }
template<int N> __device__ __forceinline__ void bulk_wait_n(){ asm volatile("cp.async.bulk.wait_group %0;" :: "n"(N) : "memory"); }
__device__ __forceinline__ void prefetch_l2(const void* p, uint32_t bytes){ asm volatile("cp.async.bulk.prefetch.L2.global [%0], %1;" :: "l"(p), "r"(bytes) : "memory"); }
__device__ __forceinline__ void wgmma_ss_n256_tb1(float (&d)[128], uint64_t descA, uint64_t descB, int scaleD) {
  asm volatile("{\n.reg .pred p;\n"
    "setp.ne.b32 p, %130, 0;\n"
    "wgmma.mma_async.sync.aligned.m64n256k16.f32.bf16.bf16 "
    "{%0, %1, %2, %3, %4, %5, %6, %7, %8, %9, %10, %11, %12, %13, %14, %15, %16, %17, %18, %19, %20, %21, %22, %23, %24, %25, %26, %27, %28, %29, %30, %31, %32, %33, %34, %35, %36, %37, %38, %39, %40, %41, %42, %43, %44, %45, %46, %47, %48, %49, %50, %51, %52, %53, %54, %55, %56, %57, %58, %59, %60, %61, %62, %63, %64, %65, %66, %67, %68, %69, %70, %71, %72, %73, %74, %75, %76, %77, %78, %79, %80, %81, %82, %83, %84, %85, %86, %87, %88, %89, %90, %91, %92, %93, %94, %95, %96, %97, %98, %99, %100, %101, %102, %103, %104, %105, %106, %107, %108, %109, %110, %111, %112, %113, %114, %115, %116, %117, %118, %119, %120, %121, %122, %123, %124, %125, %126, %127}, "
    "%128, %129, p, 1, 1, 0, 1;\n}\n"
    : "+f"(d[0]), "+f"(d[1]), "+f"(d[2]), "+f"(d[3]), "+f"(d[4]), "+f"(d[5]), "+f"(d[6]), "+f"(d[7]), "+f"(d[8]), "+f"(d[9]), "+f"(d[10]), "+f"(d[11]), "+f"(d[12]), "+f"(d[13]), "+f"(d[14]), "+f"(d[15]), "+f"(d[16]), "+f"(d[17]), "+f"(d[18]), "+f"(d[19]), "+f"(d[20]), "+f"(d[21]), "+f"(d[22]), "+f"(d[23]), "+f"(d[24]), "+f"(d[25]), "+f"(d[26]), "+f"(d[27]), "+f"(d[28]), "+f"(d[29]), "+f"(d[30]), "+f"(d[31]), "+f"(d[32]), "+f"(d[33]), "+f"(d[34]), "+f"(d[35]), "+f"(d[36]), "+f"(d[37]), "+f"(d[38]), "+f"(d[39]), "+f"(d[40]), "+f"(d[41]), "+f"(d[42]), "+f"(d[43]), "+f"(d[44]), "+f"(d[45]), "+f"(d[46]), "+f"(d[47]), "+f"(d[48]), "+f"(d[49]), "+f"(d[50]), "+f"(d[51]), "+f"(d[52]), "+f"(d[53]), "+f"(d[54]), "+f"(d[55]), "+f"(d[56]), "+f"(d[57]), "+f"(d[58]), "+f"(d[59]), "+f"(d[60]), "+f"(d[61]), "+f"(d[62]), "+f"(d[63]), "+f"(d[64]), "+f"(d[65]), "+f"(d[66]), "+f"(d[67]), "+f"(d[68]), "+f"(d[69]), "+f"(d[70]), "+f"(d[71]), "+f"(d[72]), "+f"(d[73]), "+f"(d[74]), "+f"(d[75]), "+f"(d[76]), "+f"(d[77]), "+f"(d[78]), "+f"(d[79]), "+f"(d[80]), "+f"(d[81]), "+f"(d[82]), "+f"(d[83]), "+f"(d[84]), "+f"(d[85]), "+f"(d[86]), "+f"(d[87]), "+f"(d[88]), "+f"(d[89]), "+f"(d[90]), "+f"(d[91]), "+f"(d[92]), "+f"(d[93]), "+f"(d[94]), "+f"(d[95]), "+f"(d[96]), "+f"(d[97]), "+f"(d[98]), "+f"(d[99]), "+f"(d[100]), "+f"(d[101]), "+f"(d[102]), "+f"(d[103]), "+f"(d[104]), "+f"(d[105]), "+f"(d[106]), "+f"(d[107]), "+f"(d[108]), "+f"(d[109]), "+f"(d[110]), "+f"(d[111]), "+f"(d[112]), "+f"(d[113]), "+f"(d[114]), "+f"(d[115]), "+f"(d[116]), "+f"(d[117]), "+f"(d[118]), "+f"(d[119]), "+f"(d[120]), "+f"(d[121]), "+f"(d[122]), "+f"(d[123]), "+f"(d[124]), "+f"(d[125]), "+f"(d[126]), "+f"(d[127])
    : "l"(descA), "l"(descB), "r"(scaleD));
}
__device__ __forceinline__ void wgmma_ss_n192_tb1(float (&d)[96], uint64_t descA, uint64_t descB, int scaleD) {
  asm volatile("{\n.reg .pred p;\n"
    "setp.ne.b32 p, %98, 0;\n"
    "wgmma.mma_async.sync.aligned.m64n192k16.f32.bf16.bf16 "
    "{%0, %1, %2, %3, %4, %5, %6, %7, %8, %9, %10, %11, %12, %13, %14, %15, %16, %17, %18, %19, %20, %21, %22, %23, %24, %25, %26, %27, %28, %29, %30, %31, %32, %33, %34, %35, %36, %37, %38, %39, %40, %41, %42, %43, %44, %45, %46, %47, %48, %49, %50, %51, %52, %53, %54, %55, %56, %57, %58, %59, %60, %61, %62, %63, %64, %65, %66, %67, %68, %69, %70, %71, %72, %73, %74, %75, %76, %77, %78, %79, %80, %81, %82, %83, %84, %85, %86, %87, %88, %89, %90, %91, %92, %93, %94, %95}, "
    "%96, %97, p, 1, 1, 0, 1;\n}\n"
    : "+f"(d[0]), "+f"(d[1]), "+f"(d[2]), "+f"(d[3]), "+f"(d[4]), "+f"(d[5]), "+f"(d[6]), "+f"(d[7]), "+f"(d[8]), "+f"(d[9]), "+f"(d[10]), "+f"(d[11]), "+f"(d[12]), "+f"(d[13]), "+f"(d[14]), "+f"(d[15]), "+f"(d[16]), "+f"(d[17]), "+f"(d[18]), "+f"(d[19]), "+f"(d[20]), "+f"(d[21]), "+f"(d[22]), "+f"(d[23]), "+f"(d[24]), "+f"(d[25]), "+f"(d[26]), "+f"(d[27]), "+f"(d[28]), "+f"(d[29]), "+f"(d[30]), "+f"(d[31]), "+f"(d[32]), "+f"(d[33]), "+f"(d[34]), "+f"(d[35]), "+f"(d[36]), "+f"(d[37]), "+f"(d[38]), "+f"(d[39]), "+f"(d[40]), "+f"(d[41]), "+f"(d[42]), "+f"(d[43]), "+f"(d[44]), "+f"(d[45]), "+f"(d[46]), "+f"(d[47]), "+f"(d[48]), "+f"(d[49]), "+f"(d[50]), "+f"(d[51]), "+f"(d[52]), "+f"(d[53]), "+f"(d[54]), "+f"(d[55]), "+f"(d[56]), "+f"(d[57]), "+f"(d[58]), "+f"(d[59]), "+f"(d[60]), "+f"(d[61]), "+f"(d[62]), "+f"(d[63]), "+f"(d[64]), "+f"(d[65]), "+f"(d[66]), "+f"(d[67]), "+f"(d[68]), "+f"(d[69]), "+f"(d[70]), "+f"(d[71]), "+f"(d[72]), "+f"(d[73]), "+f"(d[74]), "+f"(d[75]), "+f"(d[76]), "+f"(d[77]), "+f"(d[78]), "+f"(d[79]), "+f"(d[80]), "+f"(d[81]), "+f"(d[82]), "+f"(d[83]), "+f"(d[84]), "+f"(d[85]), "+f"(d[86]), "+f"(d[87]), "+f"(d[88]), "+f"(d[89]), "+f"(d[90]), "+f"(d[91]), "+f"(d[92]), "+f"(d[93]), "+f"(d[94]), "+f"(d[95])
    : "l"(descA), "l"(descB), "r"(scaleD));
}
__device__ __forceinline__ void wgmma_ss_n160_tb1(float (&d)[80], uint64_t descA, uint64_t descB, int scaleD) {
  asm volatile("{\n.reg .pred p;\n"
    "setp.ne.b32 p, %82, 0;\n"
    "wgmma.mma_async.sync.aligned.m64n160k16.f32.bf16.bf16 "
    "{%0, %1, %2, %3, %4, %5, %6, %7, %8, %9, %10, %11, %12, %13, %14, %15, %16, %17, %18, %19, %20, %21, %22, %23, %24, %25, %26, %27, %28, %29, %30, %31, %32, %33, %34, %35, %36, %37, %38, %39, %40, %41, %42, %43, %44, %45, %46, %47, %48, %49, %50, %51, %52, %53, %54, %55, %56, %57, %58, %59, %60, %61, %62, %63, %64, %65, %66, %67, %68, %69, %70, %71, %72, %73, %74, %75, %76, %77, %78, %79}, "
    "%80, %81, p, 1, 1, 0, 1;\n}\n"
    : "+f"(d[0]), "+f"(d[1]), "+f"(d[2]), "+f"(d[3]), "+f"(d[4]), "+f"(d[5]), "+f"(d[6]), "+f"(d[7]), "+f"(d[8]), "+f"(d[9]), "+f"(d[10]), "+f"(d[11]), "+f"(d[12]), "+f"(d[13]), "+f"(d[14]), "+f"(d[15]), "+f"(d[16]), "+f"(d[17]), "+f"(d[18]), "+f"(d[19]), "+f"(d[20]), "+f"(d[21]), "+f"(d[22]), "+f"(d[23]), "+f"(d[24]), "+f"(d[25]), "+f"(d[26]), "+f"(d[27]), "+f"(d[28]), "+f"(d[29]), "+f"(d[30]), "+f"(d[31]), "+f"(d[32]), "+f"(d[33]), "+f"(d[34]), "+f"(d[35]), "+f"(d[36]), "+f"(d[37]), "+f"(d[38]), "+f"(d[39]), "+f"(d[40]), "+f"(d[41]), "+f"(d[42]), "+f"(d[43]), "+f"(d[44]), "+f"(d[45]), "+f"(d[46]), "+f"(d[47]), "+f"(d[48]), "+f"(d[49]), "+f"(d[50]), "+f"(d[51]), "+f"(d[52]), "+f"(d[53]), "+f"(d[54]), "+f"(d[55]), "+f"(d[56]), "+f"(d[57]), "+f"(d[58]), "+f"(d[59]), "+f"(d[60]), "+f"(d[61]), "+f"(d[62]), "+f"(d[63]), "+f"(d[64]), "+f"(d[65]), "+f"(d[66]), "+f"(d[67]), "+f"(d[68]), "+f"(d[69]), "+f"(d[70]), "+f"(d[71]), "+f"(d[72]), "+f"(d[73]), "+f"(d[74]), "+f"(d[75]), "+f"(d[76]), "+f"(d[77]), "+f"(d[78]), "+f"(d[79])
    : "l"(descA), "l"(descB), "r"(scaleD));
}

namespace ssm {
constexpr int L=L_;
constexpr int U_OFF=0, V5_OFF=4352, V3_OFF=7456, V9_OFF=10560, V7_OFF=12608, R_OFF=14656, RS_OFF=16960, RF2_OFF=17184, RF3_OFF=18208;
constexpr int CH_STRIDE=19088;
constexpr int BUF_BYTES=4*CH_STRIDE;
constexpr int KT_BYTES=RF3_OFF+768-R_OFF, KT_STRIDE=4352;
constexpr int TILE_BYTES=32768;
constexpr int TB_PITCH=144, TB_ROWS=56, TB_BYTES=TB_PITCH*TB_ROWS;
constexpr int SM_TILE=0, SM_BUF=65536, SM_END=SM_BUF+2*BUF_BYTES;
static_assert(TB_BYTES<=V7_OFF-V5_OFF, "the exponential tables alias the box-sum arrays");

__device__ __forceinline__ uint32_t swz(uint32_t ch){ return ch ^ ((ch>>3)&1u); }

struct cf { float r,i; };
__device__ __forceinline__ cf cmul(cf a, cf b){ cf o; o.r=fmaf(a.r,b.r,-a.i*b.i); o.i=fmaf(a.r,b.i,a.i*b.r); return o; }
__device__ __forceinline__ cf cmulc(cf a, cf b){ cf o; o.r=fmaf(a.r,b.r,a.i*b.i); o.i=fmaf(a.i,b.r,-a.r*b.i); return o; }
__device__ __forceinline__ cf csq(cf a){ cf o; o.r=fmaf(a.r,a.r,-a.i*a.i); o.i=(a.r+a.r)*a.i; return o; }
__device__ __forceinline__ uint32_t hcmul(uint32_t p, uint32_t a, uint32_t b){
  __half2 hp=*reinterpret_cast<__half2*>(&p), ha=*reinterpret_cast<__half2*>(&a), hb=*reinterpret_cast<__half2*>(&b);
  __half2 r=__hfma2(__high2half2(hp),hb,__hmul2(__low2half2(hp),ha));
  return *reinterpret_cast<uint32_t*>(&r);
}
__device__ __forceinline__ cf cexp_p(float zr, float zi, float p){
  float m; float e=(zr*p)*1.4426950408889634f;
  asm("ex2.approx.ftz.f32 %0,%1;":"=f"(m):"f"(e));
  float th=zi*p;
  float k=rintf(th*0.15915494309189535f);
  float r=fmaf(k,-6.2831854820251465f,th); r=fmaf(k,1.7484555e-7f,r);
  cf o; o.r=m*__cosf(r); o.i=m*__sinf(r); return o;
}

struct Params { const __nv_bfloat16 *logA,*Aim,*Cr,*Ci,*logdt,*Dskip; };

__device__ __forceinline__ float bfget(uint2 v,int r){ uint32_t w=(r&2)?v.y:v.x; return (r&1)?bfhi(w):bflo(w); }

struct ChanP { uint2 la, ai, cr, ci; uint32_t ld, ds; };
__device__ __forceinline__ ChanP load_chan(const Params& P, int d, int lane){
  ChanP c;
  c.la=__ldg((const uint2*)(P.logA+d*NM)+lane); c.ai=__ldg((const uint2*)(P.Aim+d*NM)+lane);
  c.cr=__ldg((const uint2*)(P.Cr+d*NM)+lane);   c.ci=__ldg((const uint2*)(P.Ci+d*NM)+lane);
  c.ld=__ldg((const unsigned short*)P.logdt+d); c.ds=__ldg((const unsigned short*)P.Dskip+d);
  return c;
}
template<class HookF>
__device__ __forceinline__ void kgen_rounds(const ChanP& cp, uint32_t tb, int lane, int r0, int nr, float (&acc)[5][4], float& s2048, float& sc, HookF hook){
  const uint2 la4=cp.la, ai4=cp.ai, cr4=cp.cr, ci4=cp.ci;
  float dt=bf16r(expf(bflo(cp.ld)));
  float mx=0.f;
  #pragma unroll
  for(int r=0;r<4;r++) mx=fmaxf(mx,fmaxf(fabsf(bfget(cr4,r)),fabsf(bfget(ci4,r))));
  #pragma unroll
  for(int o=16;o;o>>=1) mx=fmaxf(mx,__shfl_xor_sync(0xffffffffu,mx,o));
  uint32_t eb=(__float_as_uint(mx)>>23)&0xff; eb=min(max(eb+1u,2u),252u);
  float sigma=__uint_as_float(eb<<23), isig=__uint_as_float((254u-eb)<<23);
  #pragma unroll
  for(int b=0;b<5;b++){acc[b][0]=acc[b][1]=acc[b][2]=acc[b][3]=0.f;}
  s2048=0.f;
  sc=2.f*dt*sigma;
  const uint32_t st=tb+lane*4;
  const uint32_t aA=tb+((lane&7)+8*((lane>>3)&1))*TB_PITCH+16*(lane>>4);
  const uint32_t aB=tb+(16+(lane&7))*TB_PITCH+16*(lane>>3);
  hook();
  #pragma unroll 1
  for(int r=r0;r<r0+nr;r++){
    float Ar=bf16r(expf(bfget(la4,r)));
    float zr=-Ar*dt, zi=bfget(ai4,r)*dt;
    cf H; H.r=bfget(cr4,r)*isig; H.i=-bfget(ci4,r)*isig;
    cf w1=cexp_p(zr,zi,1.f), w128=cexp_p(zr,zi,128.f);
    cf w2=csq(w1), w4=csq(w2), w8=csq(w4), w16=csq(w8);
    cf w256=csq(w128), w512=csq(w256), w1024=csq(w512);
    const uint32_t c128a=pack_hf(w128.r,-w128.i), c128b=pack_hf(w128.i,w128.r);
    const uint32_t c4a=pack_hf(w4.r,-w4.i), c4b=pack_hf(w4.i,w4.r);
    const uint32_t m8a=pack_hf(w8.r,w8.i), m8b=pack_hf(-w8.i,w8.r);
    cf hA=H, hB=cmulc(H,w256), hC=cmulc(H,w512), hD=cmulc(H,w1024);
    cf E[8]; E[1]=w16;
    #pragma unroll
    for(int n=0;n<8;n++){
      if(n) hA=cmulc(hA,w1);
      { uint32_t p=pack_hf(hA.r,hA.i); sts32(st+(16+n)*TB_PITCH,p); sts32(st+(24+n)*TB_PITCH,hcmul(p,c128a,c128b)); }
      if(n) hD=cmulc(hD,w128);
      sts32(st+(48+n)*TB_PITCH,pack_hf(hD.r,hD.i));
      if(n<4){
        if(n) hB=cmulc(hB,w2);
        uint32_t p=pack_hf(hB.r,hB.i); sts32(st+(32+n)*TB_PITCH,p); sts32(st+(36+n)*TB_PITCH,hcmul(p,c128a,c128b));
      } else {
        int q=n-4;
        if(q) hC=cmulc(hC,w128);
        uint32_t p=pack_hf(hC.r,hC.i); sts32(st+(40+2*q)*TB_PITCH,p); sts32(st+(41+2*q)*TB_PITCH,hcmul(p,c4a,c4b));
      }
      uint32_t p;
      if(n==0) p=pack_hf(1.f,0.f);
      else { if(n>1) E[n]=(n&1)?cmul(E[n-1],w16):csq(E[n>>1]); p=pack_hf(E[n].r,E[n].i); }
      sts32(st+(2*n)*TB_PITCH,p);
      sts32(st+(2*n+1)*TB_PITCH,(n==0)?m8a:hcmul(p,m8a,m8b));
    }
    s2048+=fmaf(hD.r,w128.r,hD.i*w128.i);
    __syncwarp();
    #pragma unroll
    for(int kp=0;kp<2;kp++){
      uint32_t a[2][4];
      ldsm4(aA+kp*64,a[0][0],a[0][1],a[0][2],a[0][3]);
      ldsm4(aA+kp*64+32,a[1][0],a[1][1],a[1][2],a[1][3]);
      #pragma unroll
      for(int b=0;b<5;b++){
        uint32_t b0,b1,b2,b3;
        ldsm4(aB+b*8*TB_PITCH+kp*64,b0,b1,b2,b3);
        mma_hf(acc[b],a[0][0],a[0][1],a[0][2],a[0][3],b0,b1);
        mma_hf(acc[b],a[1][0],a[1][1],a[1][2],a[1][3],b2,b3);
      }
    }
    __syncwarp();
  }
}
__device__ __forceinline__ void kgen_tables(uint32_t ch, int lane, float (&acc)[5][4], float s2048, float sc){
  const int g=lane>>2, c=lane&3;
  #pragma unroll
  for(int o=16;o;o>>=1) s2048+=__shfl_xor_sync(0xffffffffu,s2048,o);
  #pragma unroll
  for(int b=0;b<5;b++){
    #pragma unroll
    for(int i=0;i<4;i++) acc[b][i]*=sc;
  }
  s2048*=sc;
  const uint32_t R=ch+R_OFF+24*4;
  uint32_t Pq[4];
  Pq[0]=pack_bf(acc[0][0],acc[0][1]); Pq[1]=pack_bf(acc[0][2],acc[0][3]);
  Pq[2]=pack_bf(acc[1][0],acc[1][1]); Pq[3]=pack_bf(acc[1][2],acc[1][3]);
  #pragma unroll
  for(int q=0;q<4;q++){
    uint32_t prev=__shfl_up_sync(0xffffffffu,Pq[q],1);
    uint32_t t31=q? __shfl_sync(0xffffffffu,Pq[q?q-1:0],31) : 0u;
    if(lane==0) prev=t31;
    sts64(R+4*(64*q+2*lane), __byte_perm(Pq[q],prev,0x7610), __byte_perm(Pq[q],Pq[q],0x1032));
  }
  uint32_t k255=__shfl_sync(0xffffffffu,Pq[3],31);
  uint32_t C0=pack_bf(acc[3][0],acc[3][0]);
  uint32_t f512=__shfl_sync(0xffffffffu,C0,0);
  {
    uint32_t F0[2],F2[2];
    F0[0]=pack_bf(acc[2][0],acc[2][0]); F2[0]=pack_bf(acc[2][1],acc[2][1]);
    F0[1]=pack_bf(acc[2][2],acc[2][2]); F2[1]=pack_bf(acc[2][3],acc[2][3]);
    int src=((c&1)?lane+3:lane+1)&31;
    uint32_t n0=__shfl_sync(0xffffffffu,F0[0],src), n1=__shfl_sync(0xffffffffu,F0[1],src);
    uint32_t m=__shfl_sync(0xffffffffu,F0[0],2);
    bool sp=(c&1)&&(g==7);
    uint32_t nx[2]; nx[0]=sp?n1:n0; nx[1]=sp?((c==1)?m:f512):n1;
    #pragma unroll
    for(int i=0;i<2;i++){
      int p0=256+128*(c>>1)+4*(c&1)+8*(g+8*i);
      uint32_t w0=F0[i]; if(i==0 && lane==0) w0=__byte_perm(F0[0],k255,0x7610);
      sts128(R+4*p0, w0, F0[i], __byte_perm(F2[i],F0[i],0x7610), __byte_perm(nx[i],F2[i],0x7610));
    }
    if(lane==0) sts128(R+4*512, f512,f512,f512, f512&0xffff0000u);
  }
  uint32_t f1024=__shfl_sync(0xffffffffu,pack_bf(acc[4][0],acc[4][0]),0);
  {
    const uint32_t RF=ch+RF2_OFF-16*4;
    #pragma unroll
    for(int i=0;i<2;i++){
      int j=g+8*i, mu=32+8*c+(j>>1), odd=j&1;
      uint32_t v=pack_bf(acc[3][2*i],acc[3][2*i+1]);
      int x0=mu-(odd?0:1);
      if(x0>=32){ uint32_t a=RF+(odd?2:0)*256+4*x0; sts16(a,v); sts16(a+6,v); }
      uint32_t a1=RF+(odd?3:1)*256+4*mu; sts16(a1,v>>16); sts16(a1+6,v>>16);
    }
    if(lane==0){ uint32_t a=RF+4*63; sts16(a,f1024); sts16(a+6,f1024); }
  }
  {
    const uint32_t RF=ch+RF3_OFF-48*4;
    #pragma unroll
    for(int i=0;i<2;i++){
      int j=g+8*i, odd=j&1;
      uint32_t v=pack_bf(acc[4][2*i],acc[4][2*i+1]);
      #pragma unroll
      for(int e=0;e<2;e++){
        int mu=64+8*(2*c+e)+(j>>1); int x=mu-(odd?0:1);
        if(x>=64){ uint32_t a=RF+(odd?1:0)*384+4*x; uint32_t vv=e?(v>>16):v; sts16(a,vv); sts16(a+6,vv); }
      }
    }
    if(lane==0){ uint32_t v=pack_bf(s2048,0.f); uint32_t a=RF+4*127; sts16(a,v); sts16(a+6,v); }
  }
  if(lane==0){ uint32_t a=ch+RS_OFF+4*19; sts32(a,f1024&0xffffu); sts32(a+4,f1024); sts32(a+8,f1024&0xffff0000u); }
}

__device__ __forceinline__ void zero_static(uint32_t ch, int lane){
  if(lane<16) sts128(ch+U_OFF+16*lane,0,0,0,0);
  for(int i=lane;i<KT_BYTES/16;i+=32) sts128(ch+R_OFF+16*i,0,0,0,0);
}
__device__ __forceinline__ void transpose_tile(uint32_t tile, uint32_t buf, int half, int w, int lane){
  const int g=lane>>2,c=lane&3;
  const bool mine=(half==2)||((half<2)?((g>>2)==half):(g==half-8));
  const uint32_t dst=buf+((half==2)?(g>>2)*BUF_BYTES:0)+((half>=8)?0:(g&3)*CH_STRIDE)+U_OFF+4*c+16*(64*w+16);
  const uint32_t src=tile+(512*w+lane)*16;
  #pragma unroll
  for(int it=0;it<16;it++){
    uint32_t r[4]; ldsm4t(src+it*512,r[0],r[1],r[2],r[3]);
    if(mine){
      #pragma unroll
      for(int j=0;j<4;j++) sts32(dst+16*(4*it+(j^((it>>1)&1))),r[j]);
    }
  }
}
__device__ __forceinline__ void windows_channel(uint32_t ch, int lane, int it0, int step, bool tail){
  #pragma unroll 1
  for(int it=it0;it<6;it+=step){
    int q=-1+32*it+lane;
    uint4 c0=lds128(ch+U_OFF+16*swz(q+15)), c1=lds128(ch+U_OFF+16*swz(q+16)), c2=lds128(ch+U_OFF+16*swz(q+17));
    float v[20];
    v[3]=bfhi(c0.y); v[4]=bflo(c0.z); v[5]=bfhi(c0.z); v[6]=bflo(c0.w); v[7]=bfhi(c0.w);
    v[8]=bflo(c1.x); v[9]=bfhi(c1.x); v[10]=bflo(c1.y); v[11]=bfhi(c1.y); v[12]=bflo(c1.z); v[13]=bfhi(c1.z); v[14]=bflo(c1.w); v[15]=bfhi(c1.w);
    v[16]=bflo(c2.x); v[17]=bfhi(c2.x); v[18]=bflo(c2.y); v[19]=bfhi(c2.y);
    float P[21]; P[3]=0.f;
    #pragma unroll
    for(int i=3;i<20;i++) P[i+1]=P[i]+v[i];
    uint32_t o5[4],o3[4];
    #pragma unroll
    for(int e=0;e<4;e++){
      o5[e]=pack_bf(P[11+2*e]-P[6+2*e],P[12+2*e]-P[7+2*e]);
      o3[e]=pack_bf(P[6+2*e]-P[3+2*e],P[7+2*e]-P[4+2*e]);
    }
    sts128(ch+V5_OFF+16*swz(q+2),o5[0],o5[1],o5[2],o5[3]);
    sts128(ch+V3_OFF+16*swz(q+1),o3[0],o3[1],o3[2],o3[3]);
    if(it<4){
      uint32_t o9[4],o7[4];
      #pragma unroll
      for(int e=0;e<4;e++){
        o9[e]=pack_bf(P[13+2*e]-P[4+2*e],P[14+2*e]-P[5+2*e]);
        o7[e]=pack_bf(P[12+2*e]-P[5+2*e],P[13+2*e]-P[6+2*e]);
      }
      if(q<=125) sts128(ch+V9_OFF+16*swz(q+2),o9[0],o9[1],o9[2],o9[3]);
      if(q<=126) sts128(ch+V7_OFF+16*swz(q+1),o7[0],o7[1],o7[2],o7[3]);
    }
  }
  if(tail && lane==8){ sts128(ch+V5_OFF,0,0,0,0); sts128(ch+V9_OFF,0,0,0,0); }
  if(tail && lane<8){
    float s=0.f;
    #pragma unroll
    for(int i=0;i<3;i++){ int t=1523+lane+i; uint32_t a=ch+U_OFF+16*swz((t>>3)+16)+2*(t&7); unsigned short hv; asm volatile("ld.shared.u16 %0,[%1];":"=h"(hv):"r"(a)); s+=__uint_as_float((uint32_t)hv<<16); }
    sts16(ch+V3_OFF+16*swz(192)+2*lane, pack_bf(s,0.f));
  }
}
__device__ __forceinline__ void conv_channel(uint32_t ch, float dskip, int lane, uint32_t zero, int coop, uint32_t part0, uint32_t part1){
  const int da=(coop<0)?0:2*coop, db=(coop<0)?8:2*coop+2;
  const int c2a=(coop<0)?0:((coop==0)?0:(coop==3)?2:coop-1), c2b=(coop<0)?4:((coop==0)?0:(coop==3)?4:coop);
  const int c3a=(coop<0)?0:((coop==1||coop==2)?coop-1:0), c3b=(coop<0)?2:((coop==1||coop==2)?coop:0);
  const int g=lane>>2,c=lane&3, t=g-2*c;
  float acc[16][4];
  #pragma unroll
  for(int n=0;n<16;n++){acc[n][0]=acc[n][1]=acc[n][2]=acc[n][3]=0.f;}
  const uint32_t Rb=ch+R_OFF+4*(24+t);
  const uint32_t RSb=ch+RS_OFF+4*(16+t);
  #pragma unroll 1
  for(int d0=da;d0<db;d0++){
    uint32_t B[16][2];
    {
      int ap=8*(lane>>4)+(lane&7)-d0;
      uint32_t chn=2*(ap+8)+((lane>>3)&1);
      uint32_t a=ch+U_OFF+16*swz(chn);
      #pragma unroll
      for(int p=0;p<8;p++) ldsm4(a+p*512,B[2*p][0],B[2*p][1],B[2*p+1][0],B[2*p+1][1]);
    }
    uint32_t AA[4][4];
    #pragma unroll
    for(int d1=0;d1<4;d1++){
      uint32_t y=Rb+4*16*(8*d1+d0);
      AA[d1][0]=lds32(y); AA[d1][1]=lds32(y+32); AA[d1][2]=lds32(y-32); AA[d1][3]=AA[d1][0]+zero;
    }
    #pragma unroll
    for(int d1=0;d1<4;d1++){

      #pragma unroll
      for(int n=d1;n<16;n++) mma_bf(acc[n],AA[d1][0],AA[d1][1],AA[d1][2],AA[d1][3],B[n-d1][0],B[n-d1][1]);
    }
    if(d0<2){
      { uint32_t y=Rb+4*16*(32+d0);
        uint32_t a0=lds32(y), a1=lds32(y+32), a2=lds32(y-32), a3=a0+zero;
        #pragma unroll
        for(int n=4;n<16;n++) mma_bf(acc[n],a0,a1,a2,a3,B[n-4][0],B[n-4][1]); }
      { uint32_t y=RSb+4*16*d0;
        uint32_t a0=lds32(y), a1=lds32(y+32), a2=lds32(y-32), a3=a0+zero;
        #pragma unroll
        for(int n=8;n<16;n++) mma_bf(acc[n],a0,a1,a2,a3,B[n-8][0],B[n-8][1]); }
    }
  }
  const int i4=lane>>3, r8=lane&7;
  #pragma unroll 1
  for(int cb=c2a;cb<c2b;cb++){
    uint32_t arr=ch+((cb&1)?V3_OFF:V5_OFF); int sh=(cb==1||cb==2)?1:0;
    uint32_t W0[6],W1[6];
    uint32_t rf=ch+RF2_OFF+cb*256+4*(t-16);
    #pragma unroll
    for(int s=0;s<6;s++){ W0[s]=lds32(rf+4*8*(s+4)); W1[s]=s?(W0[s-1]+zero):lds32(rf+4*8*3); }
    uint32_t chn=2*(8*(i4>>1)+r8)+(i4&1)+sh;
    uint32_t a=arr+16*swz(chn);
    #pragma unroll
    for(int b=0;b<6;b++){
      uint32_t a0,a1,a2,a3; ldsm4t(a+b*512,a0,a1,a2,a3);
      #pragma unroll
      for(int s=4;s<10;s++){ int n=s+2*b; if(n<16) mma_bf(acc[n],a0,a1,a2,a3,W0[s-4],W1[s-4]); }
    }
  }
  #pragma unroll 1
  for(int cb=c3a;cb<c3b;cb++){
    uint32_t arr=ch+(cb?V7_OFF:V9_OFF);
    uint32_t W0[8],W1[8];
    uint32_t rf=ch+RF3_OFF+cb*384+4*(t-48);
    #pragma unroll
    for(int s=0;s<8;s++){ W0[s]=lds32(rf+4*8*(s+8)); W1[s]=s?(W0[s-1]+zero):lds32(rf+4*8*7); }
    uint32_t chn=2*(8*(i4>>1)+r8)+(i4&1);
    uint32_t a=arr+16*swz(chn);
    #pragma unroll
    for(int b=0;b<4;b++){
      uint32_t a0,a1,a2,a3; ldsm4t(a+b*512,a0,a1,a2,a3);
      #pragma unroll
      for(int s=8;s<16;s++){ int n=s+2*b; if(n<16) mma_bf(acc[n],a0,a1,a2,a3,W0[s-8],W1[s-8]); }
    }
  }
  if(coop>=0){
    #pragma unroll
    for(int n=0;n<16;n++)
      #pragma unroll
      for(int k=0;k<4;k++) sts32f(((n<8)?part0:part1)+((4*n+k)&31)*128+lane*4,acc[n][k]);
    return;
  }
  {
    const uint32_t dsk2=pack_bf(dskip,dskip);
    int ar=8*(i4>>1)+r8, h=i4&1;
    uint32_t chn=2*(ar+8)+h;
    uint32_t ua=ch+U_OFF+16*swz(chn);
    uint32_t oa=ch+U_OFF+16*chn;
    #pragma unroll
    for(int p=0;p<8;p++){
      uint32_t u[4]; ldsm4t(ua+p*512,u[0],u[1],u[2],u[3]);
      uint32_t o[4];
      #pragma unroll
      for(int m=0;m<4;m++){
        int n=2*p+(m>>1), k=2*(m&1);
        o[m]=badd2(pack_bf(acc[n][k],acc[n][k+1]),bmul2(u[m],dsk2));
      }
      stsm4t(oa+p*512,o[0],o[1],o[2],o[3]);
    }
  }
}
struct Coop { uint32_t tb, ts, p0, ps; };
__device__ __forceinline__ uint32_t coop_part(const Coop& cq, int w, int half){ return (w==0) ? cq.p0+half*cq.ps : cq.tb+w*cq.ts+half*4096; }
__device__ __forceinline__ void coop_epilogue(uint32_t buf, const Coop& cq, float dskip, int w, int lane){
  const int i4=lane>>3, r8=lane&7;
  const uint32_t dsk2=pack_bf(dskip,dskip);
  const int ar=8*(i4>>1)+r8, h=i4&1;
  const uint32_t chn=2*(ar+8)+h;
  const uint32_t ua=buf+U_OFF+16*swz(chn)+2*w*512, oa=buf+U_OFF+16*chn+2*w*512;
  #pragma unroll
  for(int pp=0;pp<2;pp++){
    float v[8];
    #pragma unroll
    for(int k=0;k<8;k++) v[k]=0.f;
    const int wd=16*w+8*pp;
    #pragma unroll
    for(int q=0;q<4;q++){
      const uint32_t pb=coop_part(cq,q,wd>>5)+(wd&31)*128+lane*4;
      #pragma unroll
      for(int k=0;k<8;k++) v[k]+=lds32f(pb+k*128);
    }
    uint32_t u[4]; ldsm4t(ua+pp*512,u[0],u[1],u[2],u[3]);
    uint32_t o[4];
    #pragma unroll
    for(int m=0;m<4;m++) o[m]=badd2(pack_bf(v[2*m],v[2*m+1]),bmul2(u[m],dsk2));
    stsm4t(oa+pp*512,o[0],o[1],o[2],o[3]);
  }
}
}
struct Sync { unsigned h_ready[16*4]; unsigned g_ready[16]; unsigned a_ready[4]; unsigned done; };
__device__ Sync g_sync;
__device__ __align__(1024) uint8_t g_h[16*216*2048];
__device__ __align__(1024) __nv_bfloat16 g_aT[DM*L_];
__device__ float g_gate[L_];
#define TL(i) do{}while(0)

constexpr int NTHREADS=384;
constexpr int N_G1_CLUSTERS=56, NT1=7, NT2=4, NTASKS=160;
constexpr int G2_NB=5, G2_N=32*G2_NB;
constexpr int G1_STAGES=4, G1_A=16384, G1_B=32768, G1_ST=G1_A+G1_B;
constexpr int G2_STAGES=4, G2_A=16384, G2_BLK=4096, G2_B=G2_NB*G2_BLK, G2_ST=G2_A+G2_B;
constexpr int G2_BASE=65536;
constexpr int SM_BARS=218624;
constexpr int SMEM_BYTES=SM_BARS+1024+1024;
static_assert(G1_STAGES*G1_ST<=SM_BARS && G2_BASE+G2_STAGES*G2_ST<=SM_BARS && ssm::SM_END<=SM_BARS, "smem map");
enum { B_G1F=0, B_G1E=4, B_G2F=8, B_G2E=12, B_STG=16, B_AF=17, B_TILE=18, B_SF=19, B_SE=21, B_TID=23, B_HP=27, B_A2=28, B_STG2=32, B_KR=33, B_KF=35, B_GT=37, B_OWN=38, B_COUNT=39 };
constexpr int SM_TIDS=SM_BARS+384, SM_GATE=SM_BARS+512;

struct KParams {
  ssm::Params sp;
  const __nv_bfloat16 *x, *gate_w, *w2;
  uint32_t zero;
};

__device__ __forceinline__ void ssm_role(uint32_t sb, const CUtensorMap* mapU, const ssm::Params& P, int warp, int lane, bool after_g1, int sid, int ns, int oct, int nfirst, int early, uint32_t zero, ssm::ChanP cp
){
  using namespace ssm;
  const uint32_t bars=sb+SM_BARS, tile=sb+SM_TILE;
  const uint32_t b_tile=bars+8*B_TILE, b_full=bars+8*B_SF, b_empty=bars+8*B_SE;
  const int wg=warp>>2, w=warp&3;
  const int nstat=2*nfirst, E=NTASKS-nstat;
  const int hs=(ns>0)?ns:nfirst, hid=(ns>0)?(after_g1?-1:sid):oct;
  const int KF=(E>0)?E/hs:0, NC=(E>0)?4*(E-KF*hs):0;
  const int C0=4*(nstat+KF*hs);
  const bool c6=(NC<=16) && ns>0;
  const bool have=oct<NTASKS/2;
  const int n1=have?(1+((hid>=0)?KF:0)):0;
  const int n2=have?(1+((!c6 && hid>=0 && hid<NC)?((NC-1-hid)/hs+1):0)):0;
  const int n0=(have && c6 && early>=0 && early<NC)?1:0;
  auto job=[&](int b,int i)->int{ if(b<0) return -1-(C0+early); if(i==0) return 2*oct+b; if(b==0) return nstat+hid+hs*(i-1); return -1-(C0+hid+hs*(i-1)); };
  const int b=wg-1;
  const uint32_t buf=(wg==0)?(sb+TILE_BYTES):(sb+SM_BUF+b*BUF_BYTES), own=buf+w*CH_STRIDE;
  if(wg==0){
    auto issue_tile=[&](int ch0){
      mbar_expect_tx(b_tile,TILE_BYTES);
      #pragma unroll
      for(int i=0;i<8;i++) tma2d(tile+i*4096,mapU,ch0&~7,i*256,b_tile);
    };
    if(have){
      if(after_g1) mbar_wait(bars+8*B_STG,0);
      if(w==0 && elect_one()) issue_tile(8*oct);
      mbar_wait(b_tile,0);
      transpose_tile(tile,sb+SM_BUF,2,w,lane);
      named_bar(1,128);
      if(w==0 && elect_one()){ mbar_arrive(b_full); mbar_arrive(b_full+8); }
      __syncwarp();
      int ntile=1;
      #pragma unroll 1
      for(int i=1;i<n1 || i<n2;i++){
        #pragma unroll 1
        for(int bb=0;bb<2;bb++){
          if(i>=(bb?n2:n1)) continue;
          const int j=job(bb,i), ch0=(j>=0)?4*j:(-1-j);
          if(w==0 && elect_one()) issue_tile(ch0);
          mbar_wait(b_empty+8*bb,(i&1)^1);
          mbar_wait(b_tile,ntile&1); ntile++;
          transpose_tile(tile,sb+SM_BUF+bb*BUF_BYTES,(j>=0)?(j&1):(8+(ch0&7)),w,lane);
          named_bar(1,128);
          if(w==0 && elect_one()) mbar_arrive(b_full+8*bb);
          __syncwarp();
        }
      }
      if(n0){
        const int ch0=C0+early;
        if(w==0 && elect_one()) issue_tile(ch0);
        cp=load_chan(P,ch0,lane);
        mbar_wait(bars+8*B_STG2,0);
        if(w==0) zero_static(buf,lane);
        mbar_wait(b_tile,ntile&1);
        transpose_tile(tile,buf,8+(ch0&7),w,lane);
        named_bar(1,128);
      }
    }
  } else {
    zero_static(own,lane);
    __syncwarp();
  }
  {
    auto wgbar=[&](){ if(wg==0) named_bar(1,128); else if(wg==1) named_bar(6,128); else named_bar(7,128); };
    const Coop cq = (wg==0) ? Coop{sb-8192u,8192u,sb+24576u,4096u} : Coop{buf+V5_OFF,(uint32_t)CH_STRIDE,buf+2*CH_STRIDE+U_OFF+256,(uint32_t)CH_STRIDE};
    const int nj=(wg==0)?n0:(b?n2:n1);
    int pend=-1;
    bool pend_e=false;
    auto settle=[&](){
      if(lane==0){
        if(pend>=0) bulk_wait_all();
        if(pend_e) mbar_arrive(b_empty+8*b);
        if(pend>=0) red_relaxed(&g_sync.a_ready[pend/G2_N],1u);
      }
      pend=-1; pend_e=false;
      __syncwarp();
    };
    auto chan_of=[&](int i)->int{ const int j=job(b,i); return (j<0)?(-1-j):(4*j+w); };
    if(wg>0 && after_g1 && nj>0) cp=load_chan(P,chan_of(0),lane);
    #pragma unroll 1
    for(int i=0;i<nj;i++){
      const int j=job(b,i);
      const bool coop=j<0;
      const int d=coop?(-1-j):(4*j+w);
      const uint32_t ch=coop?buf:own;
      const uint32_t tbl=(coop && w>0)?(cq.tb+w*cq.ts):(ch+V5_OFF);
      if(threadIdx.x==128 && i<2) TL(21+5*i);
      const float dsk=bflo(cp.ds);
      {
        float acc[5][4], s2048, sc;
        kgen_rounds(cp,tbl,lane,coop?w:0,coop?1:4,acc,s2048,sc,settle);
        if(coop){
          if(w>0){
            const uint32_t x=tbl+lane*4;
            #pragma unroll
            for(int q=0;q<5;q++)
              #pragma unroll
              for(int k=0;k<4;k++) sts32f(x+(4*q+k)*128,acc[q][k]);
            sts32f(x+20*128,s2048);
          }
          wgbar();
          if(w==0){
            #pragma unroll 1
            for(int ww=1;ww<4;ww++){
              const uint32_t y=cq.tb+ww*cq.ts+lane*4;
              #pragma unroll
              for(int q=0;q<5;q++)
                #pragma unroll
                for(int k=0;k<4;k++) acc[q][k]+=lds32f(y+(4*q+k)*128);
              s2048+=lds32f(y+20*128);
            }
          }
        }
        if(!coop || w==0) kgen_tables(ch,lane,acc,s2048,sc);
      }
      __syncwarp();
      if(threadIdx.x==128 && i<2) TL(22+5*i);
      if(wg>0) mbar_wait(b_full+8*b,i&1);
      if(coop) wgbar();
      if(threadIdx.x==128 && i<2) TL(23+5*i);
      windows_channel(ch,lane,coop?w:0,coop?4:1,!coop||w==0);
      __syncwarp();
      if(coop) wgbar();
      if(threadIdx.x==128 && i<2) TL(24+5*i);
      if(i+1<nj) cp=load_chan(P,chan_of(i+1),lane);
      conv_channel(ch,dsk,lane,zero,coop?w:-1,coop_part(cq,w,0),coop_part(cq,w,1));
      if(coop){ wgbar(); coop_epilogue(ch,cq,dsk,w,lane); fence_async_smem(); wgbar(); }
      else { fence_async_smem(); __syncwarp(); }
      if(threadIdx.x==128 && i<2) TL(25+5*i);
      if(!coop || w==0){
        if(lane==0){ bulk_s2g(g_aT+(size_t)d*L,ch+U_OFF+256,4096); bulk_commit(); }
        pend=d;
      }
      pend_e=(wg>0);
      __syncwarp();
    }
    settle();
  }
  if(threadIdx.x==256) TL(20);
}

__device__ __forceinline__ void gate_rows(const KParams& kp, int mt, int nt, int wi, int lane){
  const int start=19*nt, cnt=min(19,128-start);
  uint4 gw[3];
  #pragma unroll
  for(int q=0;q<3;q++){ int c=lane+32*q; gw[q]=(c<80)?__ldg((const uint4*)kp.gate_w+c):make_uint4(0,0,0,0); }
  for(int r0=wi;r0<cnt;r0+=8){
    uint4 v[4][3];
    #pragma unroll
    for(int u=0;u<4;u++){
      int r=r0+2*u;
      const uint4* xp=(const uint4*)(kp.x+(size_t)(mt*128+start+min(r,cnt-1))*DM);
      #pragma unroll
      for(int q=0;q<3;q++){ int c=lane+32*q; v[u][q]=(c<80)?__ldg(xp+c):make_uint4(0,0,0,0); }
    }
    #pragma unroll
    for(int u=0;u<4;u++){
      float s=0.f;
      #pragma unroll
      for(int q=0;q<3;q++){
        const uint32_t xv[4]={v[u][q].x,v[u][q].y,v[u][q].z,v[u][q].w}, gv[4]={gw[q].x,gw[q].y,gw[q].z,gw[q].w};
        #pragma unroll
        for(int e=0;e<4;e++){ uint32_t p=bmul2(xv[e],gv[e]); s+=bflo(p); s+=bfhi(p); }
      }
      #pragma unroll
      for(int o=16;o;o>>=1) s+=__shfl_xor_sync(0xffffffffu,s,o);
      int r=r0+2*u;
      if(lane==0 && r<cnt){ float z=bf16r(s); g_gate[mt*128+start+r]=bf16r(1.f/(1.f+expf(-z))); }
    }
  }
  __threadfence();
  named_bar(3,64);
  if(wi==0 && lane==0) red_release(&g_sync.g_ready[mt],1u);
}

__global__ void __launch_bounds__(NTHREADS,1)
gated_mix_kernel(const __grid_constant__ CUtensorMap mapX, const __grid_constant__ CUtensorMap mapW1,
                 const __grid_constant__ CUtensorMap mapW2a, const __grid_constant__ CUtensorMap mapW2b,
                 const __grid_constant__ CUtensorMap mapU, const __grid_constant__ CUtensorMap mapA,
                 const __grid_constant__ CUtensorMap mapO, const __grid_constant__ KParams kp)
{
  extern __shared__ uint8_t smem_raw[];
  const uint32_t sb=(smem_u32(smem_raw)+1023)&~1023u;
  const uint32_t bars=sb+SM_BARS;
  const int warp=__shfl_sync(0xffffffffu,threadIdx.x>>5,0), lane=threadIdx.x&31;
  const int cl=blockIdx.x>>1; const uint32_t rank=blockIdx.x&1;
  const bool g1=cl<N_G1_CLUSTERS;
  const int nt=cl%NT1, mt=2*(cl/NT1)+rank;
  const bool g2=g1 && nt<NT2;
  ssm::ChanP cp0={};
  if(!g1 && warp>=4){ const int o8=(int)blockIdx.x-2*N_G1_CLUSTERS; if(o8<NTASKS/2) cp0=ssm::load_chan(kp.sp,8*o8+4*((warp>>2)-1)+(warp&3),lane); }

  if(warp==0){
    if(elect_one()){
      #pragma unroll
      for(int s=0;s<4;s++){ mbar_init(bars+8*(B_G1F+s),1); mbar_init(bars+8*(B_G1E+s),4); mbar_init(bars+8*(B_G2F+s),1); mbar_init(bars+8*(B_G2E+s),4); mbar_init(bars+8*(B_TID+s),1); mbar_init(bars+8*(B_A2+s),1); }
      mbar_init(bars+8*B_HP,2); mbar_init(bars+8*B_KR,4); mbar_init(bars+8*(B_KR+1),4); mbar_init(bars+8*B_KF,1); mbar_init(bars+8*(B_KF+1),1); mbar_init(bars+8*B_GT,1); mbar_init(bars+8*B_OWN,2);
      mbar_init(bars+8*B_STG,1); mbar_init(bars+8*B_STG2,1); mbar_init(bars+8*B_AF,1); mbar_init(bars+8*B_TILE,1);
      mbar_init(bars+8*B_SF,1); mbar_init(bars+8*(B_SF+1),1); mbar_init(bars+8*B_SE,4); mbar_init(bars+8*(B_SE+1),4);
      asm volatile("fence.mbarrier_init.release.cluster;" ::: "memory");
      fence_async_smem();
      if(g1){
        #pragma unroll
        for(int s=0;s<2;s++){
          mbar_expect_tx(bars+8*(B_G1F+s),G1_ST);
          tma3d(sb+s*G1_ST,&mapX,0,mt*128,s,bars+8*(B_G1F+s));
          tma3d(sb+s*G1_ST+G1_A,&mapW1,0,64*s,4*nt,bars+8*(B_G1F+s));
          tma3d(sb+s*G1_ST+G1_A+16384,&mapW1,0,64*s,4*nt+2,bars+8*(B_G1F+s));
        }
        #pragma unroll
        for(int s=2;s<G1_STAGES;s++) mbar_expect_tx(bars+8*(B_G1F+s),G1_ST);
      }
    }
    __syncwarp();
  }
  asm volatile("barrier.cluster.arrive.relaxed.aligned;" ::: "memory");
  asm volatile("barrier.cluster.wait.aligned;" ::: "memory");

  if(g1){
    if(warp<4){
      if(warp==0){
        if(elect_one()){
          #pragma unroll
          for(int s=2;s<G1_STAGES;s++){
            tma3d(sb+s*G1_ST,&mapX,0,mt*128,s,bars+8*(B_G1F+s));
            tma3d_mc(sb+s*G1_ST+G1_A+rank*16384,&mapW1,0,s*64,4*nt+2*rank,bars+8*(B_G1F+s),3);
          }
          for(int kb=G1_STAGES;kb<10;kb++){
            int s=kb&3; uint32_t full=bars+8*(B_G1F+s), a=sb+s*G1_ST;
            mbar_wait(bars+8*(B_G1E+s),((kb>>2)&1)^1);
            mbar_expect_tx(full,G1_ST);
            tma3d(a,&mapX,0,mt*128,kb,full);
            tma3d_mc(a+G1_A+rank*16384,&mapW1,0,kb*64,4*nt+2*rank,full,3);
            if(kb==6){
              const uint32_t per=19760, off=(cl*2+rank)*per, tot=FF*DM*2;
              if(off<tot) prefetch_l2((const uint8_t*)kp.w2+off,min(per,tot-off));
            }
          }
          TL(0);
          if(g2){
            const uint8_t* hA=g_h+(size_t)mt*216*2048;
            auto loadB=[&](int kb,int s){
              uint32_t b=sb+G2_BASE+s*G2_ST+G2_A, full=bars+8*(B_G2F+s);
              if(rank==0) tma3d_mc(b,&mapW2a,0,kb*64,G2_NB*nt,full,3); else tma3d_mc(b+3*G2_BLK,&mapW2b,0,kb*64,G2_NB*nt+3,full,3);
            };
            auto kblock=[&](int step)->int{ if(step<4) return 4*nt+step; int q=step-4; int p=q/6; int t=nt+1+(q-6*p); if(p==3){ if(t>=6) t-=6; } else if(t>=NT1) t-=NT1; return 4*t+p; };
            int seenp=0;
            for(int step=0;step<27;step++){
              int kb=kblock(step), s=step&3, p=kb&3; uint32_t full=bars+8*(B_G2F+s);
              if(step==4){
                wait_flag(&g_sync.h_ready[mt*4],7); fence_async_global();
                TL(1);
                #pragma unroll
                for(int q=0;q<4;q++){ mbar_expect_tx(bars+8*(B_A2+q),G2_A); bulk_g2s(sb+G2_BASE+q*G2_ST,hA+(size_t)kblock(4+q)*G2_A,G2_A,bars+8*(B_A2+q)); }
              }
              mbar_wait(bars+8*(B_G2E+s),(step>>2)&1);
              mbar_expect_tx(full,(step<8)?G2_B:G2_ST);
              loadB(kb,s);
              if(step>=8){
                if(p>seenp){ wait_flag(&g_sync.h_ready[mt*4+p],(p<3)?7:6); fence_async_global(); seenp=p; }
                bulk_g2s(sb+G2_BASE+s*G2_ST,hA+(size_t)kb*G2_A,G2_A,full);
              }
            }
            mbar_wait(bars+8*B_AF,0);
            if(atomicAdd(&g_sync.done,1u)==16*NT2-1){
              for(int i=0;i<16*4;i++) g_sync.h_ready[i]=0;
              for(int i=0;i<16;i++) g_sync.g_ready[i]=0;
              for(int i=0;i<4;i++) g_sync.a_ready[i]=0;
              g_sync.done=0;
            }
          }
        }
        __syncwarp();
      } else {
        if(warp==1 && lane==0){
          if(!g2){
            const int o8=((int)gridDim.x-2*N_G1_CLUSTERS)+((cl/NT1)*(NT1-NT2)+(nt-NT2))*2+(int)rank;
            if(o8<NTASKS/2){ const size_t po=(size_t)o8*8*NM*2;
              prefetch_l2((const uint8_t*)kp.sp.logA+po,2048); prefetch_l2((const uint8_t*)kp.sp.Aim+po,2048); prefetch_l2((const uint8_t*)kp.sp.Cr+po,2048); prefetch_l2((const uint8_t*)kp.sp.Ci+po,2048); }
          }
        }
        if(warp<3) gate_rows(kp,mt,nt,warp-1,lane);
        if(g2 && warp==1){
          if(lane==0) wait_flag(&g_sync.g_ready[mt],NT1);
          __syncwarp();
          #pragma unroll
          for(int q=0;q<4;q++) sts32f(sb+SM_GATE+4*(lane+32*q),__ldcg(&g_gate[mt*128+lane+32*q]));
          __syncwarp();
          if(lane==0){
            mbar_arrive(bars+8*B_GT);
            mbar_wait(bars+8*B_STG2,0);
            mbar_wait(bars+8*B_OWN,0);
            wait_flag(&g_sync.a_ready[nt],min(G2_N,DM-G2_N*nt));
            fence_async_global();
            TL(2);
            mbar_expect_tx(bars+8*B_AF,2*G2_N*128);
            tma2d(sb,&mapA,mt*128,nt*G2_N,bars+8*B_AF);
            tma2d(sb+G2_N*128,&mapA,mt*128+64,nt*G2_N,bars+8*B_AF);
          }
          __syncwarp();
        }
        if(warp==3 && lane==0){
          const int npiece=(nt<6)?4:3;
          mbar_wait(bars+8*B_HP,0);
          unsigned* fl=&g_sync.h_ready[mt*4];
          auto put=[&](int p){ bulk_s2g(g_h+((size_t)mt*216+nt*32+8*p)*2048,sb+p*16384,16384); bulk_commit(); };
#define PACE 0
          if(PACE==0){
            put(0); put(1); TL(11);
            bulk_wait_n<1>(); TL(12); red_relaxed(fl,1u);
            bulk_wait_n<0>(); red_relaxed(fl+1,1u);
            mbar_arrive(bars+8*B_STG);
            if(npiece==4) wait_flag(fl+1,7);
            put(2); if(npiece==4) put(3);
            bulk_wait_all(); red_relaxed(fl+2,1u); if(npiece==4) red_relaxed(fl+3,1u);
          } else {
            put(0); TL(11);
            bulk_wait_all(); TL(12); red_relaxed(fl,1u);
            wait_flag(fl,7);
            __nanosleep(PACE);
            put(1); bulk_wait_all(); red_relaxed(fl+1,1u);
            mbar_arrive(bars+8*B_STG);
            put(2); if(npiece==4) put(3);
            bulk_wait_all(); red_relaxed(fl+2,1u); if(npiece==4) red_relaxed(fl+3,1u);
          }
          mbar_arrive(bars+8*B_STG2);
          TL(5);
        }
        __syncwarp();
      }
    } else {
      const int wg=(warp>>2)-1, w=warp&3;
      {
        float d[128];
        #pragma unroll
        for(int i=0;i<128;i++) d[i]=0.f;
        if(nt<6){
        #pragma unroll 1
        for(int kb=0;kb<10;kb++){
          int s=kb&3;
          mbar_wait(bars+8*(B_G1F+s),(kb>>2)&1);
          if(kb==0 && threadIdx.x==128) TL(3);
          uint32_t a=sb+s*G1_ST+wg*8192, b=sb+s*G1_ST+G1_A;
          const uint64_t da=mkdesc(a,16,1024,1), db=mkdesc(b,8192,1024,1);
          wg_fence();
          #pragma unroll
          for(int k=0;k<4;k++) wgmma_ss_n256_tb1(d,da+2*k,db+128*k,1);
          wg_commit();
          if(kb>0){
            wg_wait<1>();
            if((threadIdx.x&127)==0){ int sp=(kb-1)&3; mbar_arrive_cluster(bars+8*(B_G1E+sp),0); mbar_arrive_cluster(bars+8*(B_G1E+sp),1); }
          }
        }
        wg_wait<0>();
        } else {
        float (&d96)[96]=*reinterpret_cast<float(*)[96]>(&d[0]);
        #pragma unroll 1
        for(int kb=0;kb<10;kb++){
          int s=kb&3;
          mbar_wait(bars+8*(B_G1F+s),(kb>>2)&1);
          if(kb==0 && threadIdx.x==128) TL(3);
          uint32_t a=sb+s*G1_ST+wg*8192, b=sb+s*G1_ST+G1_A;
          const uint64_t da=mkdesc(a,16,1024,1), db=mkdesc(b,8192,1024,1);
          wg_fence();
          #pragma unroll
          for(int k=0;k<4;k++) wgmma_ss_n192_tb1(d96,da+2*k,db+128*k,1);
          wg_commit();
          if(kb>0){
            wg_wait<1>();
            if((threadIdx.x&127)==0){ int sp=(kb-1)&3; mbar_arrive_cluster(bars+8*(B_G1E+sp),0); mbar_arrive_cluster(bars+8*(B_G1E+sp),1); }
          }
        }
        wg_wait<0>();
        }
        if(threadIdx.x==128) TL(4);
        if(g2 && (threadIdx.x&127)==0){
          #pragma unroll
          for(int s=0;s<G2_STAGES;s++){ mbar_arrive_cluster(bars+8*(B_G2E+s),0); mbar_arrive_cluster(bars+8*(B_G2E+s),1); }
        }
        named_bar(2,256);
        const int mi=lane>>3, r=lane&7;
        const uint32_t base=sb+(mi>>1)*2048+(wg*8+w*2+(mi&1))*128+r*16;
        #pragma unroll
        for(int j=0;j<32;j+=2)
          stsm4(base+j*2048,pack_bf_relu(d[4*j],d[4*j+1]),pack_bf_relu(d[4*j+2],d[4*j+3]),pack_bf_relu(d[4*j+4],d[4*j+5]),pack_bf_relu(d[4*j+6],d[4*j+7]));
        fence_async_smem();
        if(wg==0) named_bar(4,128); else named_bar(5,128);
        if(w==0 && lane==0) mbar_arrive(bars+8*B_HP);
        if(threadIdx.x==128) TL(10);
      }
      if(g2){
        float d[G2_N/2];
        #pragma unroll
        for(int i=0;i<G2_N/2;i++) d[i]=0.f;
        int s=0, par=0;
        #pragma unroll 1
        for(int kb=0;kb<27;kb++){
          mbar_wait(bars+8*(B_G2F+s),par);
          if(kb>=4 && kb<8) mbar_wait(bars+8*(B_A2+kb-4),0);
          if(kb==0 && threadIdx.x==128) TL(6);
          uint32_t a=((kb<4)?(sb+kb*16384):(sb+G2_BASE+s*G2_ST))+wg*1024, b=sb+G2_BASE+s*G2_ST+G2_A;
          const uint64_t da=mkdesc(a,2048,128,0), db=mkdesc(b,G2_BLK,512,2);
          wg_fence();
          #pragma unroll
          for(int k=0;k<4;k++) wgmma_ss_n160_tb1(d,da+256*k,db+64*k,1);
          wg_commit();
          if(kb>0){
            wg_wait<1>();
            if((threadIdx.x&127)==0){ int sp=(s==0)?G2_STAGES-1:s-1; mbar_arrive_cluster(bars+8*(B_G2E+sp),0); mbar_arrive_cluster(bars+8*(B_G2E+sp),1);
              if(kb==4) mbar_arrive(bars+8*B_OWN); }
          }
          if(++s==G2_STAGES){ s=0; par^=1; }
        }
        wg_wait<0>();
        if(threadIdx.x==128) TL(7);
        asm volatile("barrier.cluster.arrive.relaxed.aligned;" ::: "memory");
        mbar_wait(bars+8*B_GT,0);
        const int grow=wg*64+w*16+(lane>>2);
        const float g0=lds32f(sb+SM_GATE+4*grow), g1v=lds32f(sb+SM_GATE+4*(grow+8));
        const uint32_t gp[2]={pack_bf(g0,g0),pack_bf(g1v,g1v)};
        const uint32_t hp[2]={pack_bf(1.f-g0,1.f-g0),pack_bf(1.f-g1v,1.f-g1v)};
        uint32_t tb[G2_N/4];
        #pragma unroll
        for(int k=0;k<G2_N/4;k++) tb[k]=bmul2(hp[k&1],pack_bf(d[2*k],d[2*k+1]));
        if(threadIdx.x==128) TL(26);
        named_bar(2,256);
        if(threadIdx.x==128) TL(27);
        mbar_wait(bars+8*B_AF,0);
        if(threadIdx.x==128) TL(8);
        const int mi=lane>>3, r=lane&7;
        const uint32_t stg=sb+G2_BASE+wg*(G2_NB*4096);
        #pragma unroll
        for(int jj=0;jj<G2_N/8;jj+=2){
          int drow=8*(jj+(mi>>1))+r, c8=2*w+(mi&1);
          uint32_t av[4]; ldsm4t(sb+wg*(G2_N*128)+drow*128+((c8^(drow&7))<<4),av[0],av[1],av[2],av[3]);
          uint32_t o[4];
          #pragma unroll
          for(int m=0;m<4;m++) o[m]=badd2(bmul2(gp[m&1],av[m]),tb[2*jj+m]);
          int j2=jj+(mi>>1), orow=w*16+8*(mi&1)+r;
          stsm4(stg+(j2>>2)*4096+orow*64+(((j2&3)^((orow>>1)&3))<<4),o[0],o[1],o[2],o[3]);
        }
        if(threadIdx.x==128) TL(28);
        fence_async_smem();
        if(wg==0) named_bar(4,128); else named_bar(5,128);
        if(threadIdx.x==128) TL(29);
        if((threadIdx.x&127)==0){
          tma3d_store(&mapO,stg,0,mt*128+wg*64,G2_NB*nt);
          bulk_commit();
          bulk_wait_read();
          if(threadIdx.x==128) TL(9);
        }
        __syncwarp();
      }
    }
  }
  if(!g2){
    const int ns=(int)gridDim.x-2*N_G1_CLUSTERS;
    const int oct=g1?(ns+((cl/NT1)*(NT1-NT2)+(nt-NT2))*2+(int)rank):((int)blockIdx.x-2*N_G1_CLUSTERS);
    ssm_role(sb,&mapU,kp.sp,warp,lane,g1,(int)blockIdx.x-2*N_G1_CLUSTERS,ns,oct,ns+16*(NT1-NT2),(g1 && nt==6)?(2*(cl/NT1)+(int)rank):-1,kp.zero,cp0
    );
  }
  if(!(g2 && warp>=4)) asm volatile("barrier.cluster.arrive.relaxed.aligned;" ::: "memory");
  asm volatile("barrier.cluster.wait.aligned;" ::: "memory");
}
}
namespace {
typedef CUresult (*PFN_encodeTiled)(CUtensorMap*, CUtensorMapDataType, cuuint32_t, void*, const cuuint64_t*, const cuuint64_t*, const cuuint32_t*, const cuuint32_t*,
                                    CUtensorMapInterleave, CUtensorMapSwizzle, CUtensorMapL2promotion, CUtensorMapFloatOOBfill);
PFN_encodeTiled g_encode=nullptr;
CUtensorMap make_map(const void* base, int rank, const cuuint64_t* dims, const cuuint64_t* strides, const cuuint32_t* box, CUtensorMapSwizzle sw){
  CUtensorMap m; cuuint32_t es[3]={1,1,1};
  g_encode(&m,CU_TENSOR_MAP_DATA_TYPE_BFLOAT16,rank,(void*)base,dims,strides,box,es,CU_TENSOR_MAP_INTERLEAVE_NONE,sw,
           CU_TENSOR_MAP_L2_PROMOTION_L2_128B,CU_TENSOR_MAP_FLOAT_OOB_FILL_NONE);
  return m;
}
CUtensorMap map3(const void* b, cuuint64_t d0,cuuint64_t d1,cuuint64_t d2,cuuint64_t s1,cuuint64_t s2,cuuint32_t b0,cuuint32_t b1,cuuint32_t b2,CUtensorMapSwizzle sw){
  cuuint64_t dims[3]={d0,d1,d2}, str[2]={s1,s2}; cuuint32_t box[3]={b0,b1,b2}; return make_map(b,3,dims,str,box,sw); }
CUtensorMap map2(const void* b, cuuint64_t d0,cuuint64_t d1,cuuint64_t s1,cuuint32_t b0,cuuint32_t b1,CUtensorMapSwizzle sw){
  cuuint64_t dims[2]={d0,d1}, str[1]={s1}; cuuint32_t box[2]={b0,b1}; return make_map(b,2,dims,str,box,sw); }
}

extern "C" void kernel_launch(void* const* d_in, const int* in_sizes, int n_in, void* d_out, int out_size){
  (void)in_sizes; (void)n_in; (void)out_size;
  static int grid=0; static void* aT=nullptr;
  if(!grid){
    void* p=nullptr; cudaDriverEntryPointQueryResult q;
    cudaGetDriverEntryPoint("cuTensorMapEncodeTiled",&p,cudaEnableDefault,&q);
    g_encode=(PFN_encodeTiled)p;
    cudaFuncSetAttribute(gated_mix_kernel,cudaFuncAttributeMaxDynamicSharedMemorySize,SMEM_BYTES);
    cudaGetSymbolAddress(&aT,g_aT);
    cudaLaunchConfig_t cfg={}; cfg.gridDim=dim3(132); cfg.blockDim=dim3(NTHREADS); cfg.dynamicSmemBytes=SMEM_BYTES;
    cudaLaunchAttribute at[1]; at[0].id=cudaLaunchAttributeClusterDimension; at[0].val.clusterDim.x=2; at[0].val.clusterDim.y=1; at[0].val.clusterDim.z=1;
    cfg.attrs=at; cfg.numAttrs=1;
    int nc=0; cudaOccupancyMaxActiveClusters(&nc,gated_mix_kernel,&cfg);
    if(nc>66) nc=66;
    if(nc<N_G1_CLUSTERS) nc=N_G1_CLUSTERS;
    grid=2*nc;
  }
  const __nv_bfloat16* x=(const __nv_bfloat16*)d_in[0];
  const __nv_bfloat16* w1=(const __nv_bfloat16*)d_in[8];
  const __nv_bfloat16* w2=(const __nv_bfloat16*)d_in[9];
  KParams kp;
  kp.sp.logA=(const __nv_bfloat16*)d_in[1]; kp.sp.Aim=(const __nv_bfloat16*)d_in[2]; kp.sp.Cr=(const __nv_bfloat16*)d_in[3];
  kp.sp.Ci=(const __nv_bfloat16*)d_in[4]; kp.sp.logdt=(const __nv_bfloat16*)d_in[5]; kp.sp.Dskip=(const __nv_bfloat16*)d_in[6];
  kp.zero=0; kp.x=x; kp.w2=w2; kp.gate_w=(const __nv_bfloat16*)d_in[10];
  CUtensorMap mX =map3(x, 64,L_,10, DM*2,128, 64,128,1, CU_TENSOR_MAP_SWIZZLE_128B);
  CUtensorMap mW1=map3(w1,64,DM,27, FF*2,128, 64,64,2,  CU_TENSOR_MAP_SWIZZLE_128B);
  CUtensorMap mW2a=map3(w2,32,FF,20, DM*2,64, 32,64,3,  CU_TENSOR_MAP_SWIZZLE_64B);
  CUtensorMap mW2b=map3(w2,32,FF,20, DM*2,64, 32,64,2,  CU_TENSOR_MAP_SWIZZLE_64B);
  CUtensorMap mU =map2(x, DM,L_, DM*2, 8,256, CU_TENSOR_MAP_SWIZZLE_NONE);
  CUtensorMap mA =map2(aT,L_,DM, L_*2, 64,G2_N, CU_TENSOR_MAP_SWIZZLE_128B);
  CUtensorMap mO =map3(d_out,32,L_,20, DM*2,64, 32,64,G2_NB, CU_TENSOR_MAP_SWIZZLE_64B);
  cudaLaunchConfig_t cfg={}; cfg.gridDim=dim3(grid); cfg.blockDim=dim3(NTHREADS); cfg.dynamicSmemBytes=SMEM_BYTES; cfg.stream=cudaStreamPerThread;
  cudaLaunchAttribute at[1]; at[0].id=cudaLaunchAttributeClusterDimension; at[0].val.clusterDim.x=2; at[0].val.clusterDim.y=1; at[0].val.clusterDim.z=1;
  cfg.attrs=at; cfg.numAttrs=1;
  cudaLaunchKernelEx(&cfg,gated_mix_kernel,mX,mW1,mW2a,mW2b,mU,mA,mO,kp);
}
```
